```python
import torch

def _softmax(x, axis=-1):
    return torch.softmax(x, dim=axis)
def _gelu(x):
    return torch.nn.functional.gelu(x, approximate="tanh")
def _silu(x):
    return torch.nn.functional.silu(x)
def _sigmoid(x):
    return torch.sigmoid(x)
def _layernorm(x, axis=-1, eps=1e-5):
    m = x.mean(dim=axis, keepdim=True)
    v = x.var(dim=axis, keepdim=True, unbiased=False)
    return (x - m) / torch.sqrt(v + eps)
def _scatter_add(tgt, idx, src, axis=0):
    return tgt.clone().index_add_(axis, idx, src)
def _segment_sum(src, seg, n):
    out = torch.zeros((n,) + src.shape[1:], dtype=src.dtype)
    return out.index_add_(0, seg, src)
def _pad(x, pw):
    flat = tuple(v for pair in reversed(pw) for v in pair)
    return torch.nn.functional.pad(x, flat)

kernel_name = 'parallel_sum__ssm_conv_h3__glu_gated_bilinear__prompt'

def setup_inputs():

    _w = (lambda a: (lambda t: t.to(torch.bfloat16) if t.is_floating_point() else t)(torch.as_tensor(a)))
    def _A_setup():
        B, S, D = 1, 2048, 512
        ks = 4
        return {
            "q": _w((lambda *s: torch.randn(*s, dtype=torch.bfloat16) * 0.05)(B, S, D)),
            "k": _w((lambda *s: torch.randn(*s, dtype=torch.bfloat16) * 0.2)(B, S, D)),
            "v": _w((lambda *s: torch.randn(*s, dtype=torch.bfloat16) * 0.2)(B, S, D)),
            "shift_k": _w((lambda *s: torch.randn(*s, dtype=torch.bfloat16) * 0.2)(D, ks) * 0.5),
            "ssm_k": _w((lambda *s: torch.randn(*s, dtype=torch.bfloat16) * 0.4)(D, S) * (1.0 / S ** 0.5)),
            "ssm_D": _w((lambda *s: torch.randn(*s, dtype=torch.bfloat16) * 0.2)(D)),
        }
    _A_in = _A_setup()

    def _B_setup():
        B, S, D, F = 1, 2048, 512, 1792
        return {
            "x": _w((lambda *s: torch.randn(*s, dtype=torch.bfloat16) * 0.05)(B, S, D)),
            "w_gate": _w((lambda *s: torch.randn(*s, dtype=torch.bfloat16) * 0.2)(D, F) * (D ** -0.5)),
            "w_up": _w((lambda *s: torch.randn(*s, dtype=torch.bfloat16) * 0.2)(D, F) * (D ** -0.5)),
            "w_down": _w((lambda *s: torch.randn(*s, dtype=torch.bfloat16) * 0.2)(F, D) * (F ** -0.5)),
        }
    _B_in = _B_setup()

    return {
        "A_q": _A_in["q"],
        "A_k": _A_in["k"],
        "A_v": _A_in["v"],
        "A_shift_k": _A_in["shift_k"],
        "A_ssm_k": _A_in["ssm_k"],
        "A_ssm_D": _A_in["ssm_D"],
        "B_x": _B_in["x"],
        "B_w_gate": _B_in["w_gate"],
        "B_w_up": _B_in["w_up"],
        "B_w_down": _B_in["w_down"],
    }

def reference(A_q, A_k, A_v, A_shift_k, A_ssm_k, A_ssm_D, B_x, B_w_gate, B_w_up, B_w_down):
    def _A_ref(q, k, v, shift_k, ssm_k, ssm_D):
        B, S, D = q.shape
        ks = shift_k.shape[-1]
        k_pad = _pad(k, ((0, 0), (ks - 1, 0), (0, 0)))
        k_shift = torch.zeros_like(k)
        for t in range(ks):
            k_shift = k_shift + k_pad[:, t:t + S, :] * shift_k[:, ks - 1 - t][None, None, :]
        kv = k_shift * v
        L = 2 * S
        kv_pad = _pad(kv, ((0, 0), (0, S), (0, 0)))
        kf_pad = _pad(ssm_k, ((0, 0), (0, S)))
        kv_f = (lambda x, axes=(-2,-1): torch.fft.rfft2(x.float(), dim=axes))(kv_pad[:, None, :, :], axes=(1, 2))
        kf_f = (lambda x, axes=(-2,-1): torch.fft.rfft2(x.float(), dim=axes))(kf_pad[:, None, :], axes=(1, 2))
        kf_f = (lambda x, *d: x.permute(*d))(kf_f, 1, 2, 0)
        y_f = kv_f * kf_f[None, :, :, :]
        y = (lambda x, s, axes=(-2,-1): torch.fft.irfft2(x, s=s, dim=axes).to(torch.bfloat16))(y_f, (1, L), axes=(1, 2))[:, 0, :S, :]
        y = y + kv * ssm_D[None, None, :]
        return q * y

    def _B_ref(x, w_gate, w_up, w_down):
        g = torch.einsum("bsd,df->bsf", x, w_gate)
        u = torch.einsum("bsd,df->bsf", x, w_up)
        h = g * u
        return torch.einsum("bsf,fd->bsd", h, w_down)

    x = A_q
    xn = _layernorm(x, axis=-1)
    return x + _A_ref(xn, A_k, A_v, A_shift_k, A_ssm_k, A_ssm_D) + _B_ref(xn, B_w_gate, B_w_up, B_w_down)
```

```cpp
#include <cuda_runtime.h>
#include <cuda_bf16.h>
#include <cuda.h>
#include <stdint.h>
#include <type_traits>

#define KV_GATE 4
#define G2_HOLD1 10
#define G2_HOLD2 20

namespace {

constexpr int SEQ = 2048, DM = 512, FF = 1792;
constexpr int NCTA = 128;

__device__ __align__(1024) uint4 g_kvT[DM * 128 * 2];
__device__ __align__(1024) __nv_bfloat16 g_h[SEQ * FF];
__device__ __align__(1024) __nv_bfloat16 g_zT[DM * SEQ];
__device__ __align__(128) uint2 g_stats[SEQ];
__device__ __align__(128) uint4 g_cs[8 * 2 * (FF / 2)];
__device__ __align__(128) unsigned g_cnt[64 * 32];
constexpr int C_DONE = 0, C_Z = 2, C_KV = 10, C_H = 16;

constexpr uint32_t SM_X = 0;
constexpr uint32_t SM_RING = 131072;
constexpr uint32_t KV_PAD = 384, KV_HALF = KV_PAD + 2048;
constexpr uint32_t TAB_P = 144, TAB_BUF = 34 * TAB_P;
constexpr uint32_t CV_TAB = 2 * KV_HALF, CV_RED = CV_TAB + 2 * TAB_BUF, CV_H = CV_TAB + 4 * TAB_BUF, CV_HBUF = 4128, CV_KVST = 5120;
constexpr uint32_t SM_CVA = 196608;
constexpr uint32_t SM_CVB = 0, SM_FX = 32768, SM_G2 = SM_FX + 16384, G2_STAGE = 24576;
constexpr int G2_NB = 6;
__device__ __forceinline__ uint32_t g2_off(int buf) { return SM_G2 + buf * G2_STAGE; }
constexpr uint32_t SM_FZ = SM_CVA;
constexpr uint32_t SM_CS = SM_RING + 6 * 16384;
static_assert(CV_H + 2 * CV_HBUF <= SM_FX && SM_G2 + G2_NB * G2_STAGE <= SM_CVA && SM_CVA + CV_H + 2 * CV_HBUF <= SM_CS, "smem");
constexpr uint32_t SM_ST = SM_CS + 1792;
constexpr uint32_t SM_BAR = SM_ST + 512;
constexpr uint32_t SMEM_TOTAL = SM_BAR + 64 * 8;
static_assert(SMEM_TOTAL <= 232448, "smem");
static_assert(CV_TAB % 16 == 0 && SM_BAR % 8 == 0, "align");
constexpr int B_XFULL = 0, B_WFULL = 8, B_WEMPTY = 12, B_XFREE = 16, B_G2FULL = 24, B_G2EMPTY = 32, B_PREP = 39,
              B_HKA = 40, B_FINZ = 41, B_H1RDY = 42  , B_HKB = 44  , B_ST2 = 46, B_HDONE = 48, B_SP0DONE = 51, B_KVGATE = 52, B_FIN = 53, B_H0RDY = 54, B_KVRDY = 55, B_PREP1 = 56  , B_AFREE = 58, B_CVP = 60  , B_PREP2 = 62;
constexpr uint32_t BAR_CODES = (1u << 6) | (1u << 8) | (1u << 10) | (2u << 16) | (2u << 18) | (1u << 24) | (2u << 30);

__constant__ int c_atom[28] = {0, 5, 7, 12, 14, 19, 21, 26,  1, 6, 8, 13, 15, 20, 22, 27,  2, 4, 9, 11, 16, 18, 23, 25, 3, 10, 17, 24};

struct Maps { CUtensorMap x, w, wh, wd, out, z, kv; };
struct Ptrs {
  const __nv_bfloat16 *x, *k, *v, *shift_k, *ssm_k, *ssm_D, *w0, *w1, *wd;
};

__device__ __forceinline__ uint32_t smem_u32(const void* p) { return (uint32_t)__cvta_generic_to_shared(p); }
__device__ __forceinline__ void mbar_init(uint32_t bar, uint32_t cnt) { asm volatile("mbarrier.init.shared::cta.b64 [%0], %1;" :: "r"(bar), "r"(cnt) : "memory"); }
__device__ __forceinline__ void mbar_expect_tx(uint32_t bar, uint32_t bytes) { asm volatile("mbarrier.arrive.expect_tx.shared::cta.b64 _, [%0], %1;" :: "r"(bar), "r"(bytes) : "memory"); }
__device__ __forceinline__ void mbar_arrive(uint32_t bar) { asm volatile("mbarrier.arrive.shared::cta.b64 _, [%0];" :: "r"(bar) : "memory"); }
__device__ __forceinline__ bool mbar_try(uint32_t bar, uint32_t parity) {
  uint32_t ok;
  asm volatile("{\n.reg .pred p;\nmbarrier.try_wait.parity.shared::cta.b64 p, [%1], %2;\nselp.u32 %0, 1, 0, p;\n}\n" : "=r"(ok) : "r"(bar), "r"(parity) : "memory");
  return ok;
}
__device__ __forceinline__ bool mbar_test(uint32_t bar, uint32_t parity) {
  uint32_t ok;
  asm volatile("{\n.reg .pred p;\nmbarrier.test_wait.parity.shared::cta.b64 p, [%1], %2;\nselp.u32 %0, 1, 0, p;\n}\n" : "=r"(ok) : "r"(bar), "r"(parity) : "memory");
  return ok;
}
__device__ __forceinline__ void mbar_wait(uint32_t bar, uint32_t parity) {
  uint32_t n = 0;
  while (!mbar_try(bar, parity)) { if (++n > (1u << 22)) __trap(); }
}
__device__ __forceinline__ void mbar_wait_nt(uint32_t bar, uint32_t parity) {
  uint32_t n = 0;
  while (!mbar_try(bar, parity)) { if (++n > (1u << 18)) break; }
}
__device__ __forceinline__ unsigned ld_relaxed(const unsigned* p) { unsigned v; asm volatile("ld.relaxed.gpu.global.u32 %0, [%1];" : "=r"(v) : "l"(p)); return v; }
__device__ __forceinline__ unsigned ld_relaxed_v(const unsigned* p) { unsigned v; asm volatile("ld.relaxed.gpu.global.u32 %0, [%1];" : "=r"(v) : "l"(p) : "memory"); return v; }
__device__ __forceinline__ uint4 ld_relaxed128(const void* p) { uint4 v; asm volatile("ld.relaxed.gpu.global.v4.u32 {%0,%1,%2,%3}, [%4];" : "=r"(v.x), "=r"(v.y), "=r"(v.z), "=r"(v.w) : "l"(p) : "memory"); return v; }
__device__ __forceinline__ void st_relaxed128(void* p, uint32_t a, uint32_t b, uint32_t c, uint32_t d) { asm volatile("st.relaxed.gpu.global.v4.u32 [%0], {%1,%2,%3,%4};" :: "l"(p), "r"(a), "r"(b), "r"(c), "r"(d) : "memory"); }
__device__ __forceinline__ void st_relaxed64(void* p, uint32_t a, uint32_t b) { asm volatile("st.relaxed.gpu.global.v2.u32 [%0], {%1,%2};" :: "l"(p), "r"(a), "r"(b) : "memory"); }
__device__ __forceinline__ void sts64(uint32_t a, float x, float y) { asm volatile("st.shared.v2.f32 [%0], {%1,%2};" :: "r"(a), "f"(x), "f"(y) : "memory"); }
__device__ __forceinline__ uint4 poll_cs(int pair, unsigned tag) {
  uint32_t n = 0;
  while (true) {
    const uint4 a = ld_relaxed128(g_cs + pair), c = ld_relaxed128(g_cs + FF / 2 + pair);
    if (a.y == tag && a.w == tag && c.y == tag && c.w == tag) return make_uint4(a.x, a.z, c.x, c.z);
    __nanosleep(150);
    if (++n > (1u << 20)) __trap();
  }
}
__device__ __forceinline__ float2 poll_cs8(int mat, int pair, unsigned tag) {
  const uint4* p = g_cs + mat * (FF / 2) + pair;
  uint32_t n = 0;
  while (true) {
    uint4 v[8];
#pragma unroll
    for (int q = 0; q < 8; q++) v[q] = ld_relaxed128(p + q * FF);
    uint32_t bad = 0;
    float2 r = make_float2(0.f, 0.f);
#pragma unroll
    for (int q = 0; q < 8; q++) { bad |= (v[q].y ^ tag) | (v[q].w ^ tag); r.x += __uint_as_float(v[q].x); r.y += __uint_as_float(v[q].z); }
    if (bad == 0) return r;
    __nanosleep(150);
    if (++n > (1u << 20)) __trap();
  }
}
__device__ __forceinline__ uint2 poll_stats(int s, unsigned tag) {
  uint32_t n = 0;
  uint4 v = ld_relaxed128(&g_stats[s]);
  while (v.y != tag || v.w != tag) {
    if (++n > (1u << 16)) break;
    __nanosleep(100);
    v = ld_relaxed128(&g_stats[s]);
  }
  return make_uint2(v.x, v.z);
}
__device__ __forceinline__ void red_release(unsigned* p) { asm volatile("fence.acq_rel.gpu;\nred.relaxed.gpu.global.add.u32 [%0], 1;" :: "l"(p) : "memory"); }
__device__ __forceinline__ void spin_counter(const unsigned* p, unsigned target) {
  uint32_t n = 0;
  while ((int)(ld_relaxed_v(p) - target) < 0) { __nanosleep(64); if (++n > (1u << 21)) __trap(); }
}
__device__ __forceinline__ int fresh_tid() { int v; asm volatile("mov.u32 %0, %%tid.x;" : "=r"(v)); return v; }
__device__ __forceinline__ bool elect_one() {
  uint32_t p;
  asm volatile("{\n.reg .pred q;\nelect.sync _|q, 0xffffffff;\nselp.u32 %0, 1, 0, q;\n}\n" : "=r"(p));
  return p != 0;
}
__device__ __forceinline__ float4 lds128f(uint32_t a) { float4 v; asm volatile("ld.shared.v4.f32 {%0,%1,%2,%3}, [%4];" : "=f"(v.x), "=f"(v.y), "=f"(v.z), "=f"(v.w) : "r"(a) : "memory"); return v; }
__device__ __forceinline__ void fence_async_smem() { asm volatile("fence.proxy.async.shared::cta;" ::: "memory"); }
__device__ __forceinline__ void named_bar_r(int id, int n) { asm volatile("bar.sync %0, %1;" :: "r"(id), "r"(n) : "memory"); }
__device__ __forceinline__ void named_arrive_r(int id, int n) { asm volatile("bar.arrive %0, %1;" :: "r"(id), "r"(n) : "memory"); }
__device__ __forceinline__ void bulk_store(void* dst, uint32_t src, uint32_t bytes) {
  asm volatile("cp.async.bulk.global.shared::cta.bulk_group [%0], [%1], %2;\ncp.async.bulk.commit_group;" :: "l"(dst), "r"(src), "r"(bytes) : "memory");
}
__device__ __forceinline__ void publish_bulk(unsigned* flag) {
  asm volatile("cp.async.bulk.wait_group 0;\nfence.acq_rel.gpu;\nred.relaxed.gpu.global.add.u32 [%0], 1;" :: "l"(flag) : "memory");
}
__device__ __forceinline__ void ldmatrix_x4(uint32_t a, uint32_t& r0, uint32_t& r1, uint32_t& r2, uint32_t& r3) {
  asm volatile("ldmatrix.sync.aligned.m8n8.x4.shared.b16 {%0,%1,%2,%3}, [%4];" : "=r"(r0), "=r"(r1), "=r"(r2), "=r"(r3) : "r"(a) : "memory");
}
template <int ID, int N> __device__ __forceinline__ void named_bar() { asm volatile("bar.sync %0, %1;" :: "n"(ID), "n"(N) : "memory"); }
__device__ __forceinline__ void tma_2d(uint32_t dst, const CUtensorMap* m, int c0, int c1, uint32_t bar) {
  asm volatile("cp.async.bulk.tensor.2d.shared::cluster.global.mbarrier::complete_tx::bytes [%0], [%1, {%3, %4}], [%2];" :: "r"(dst), "l"(m), "r"(bar), "r"(c0), "r"(c1) : "memory");
}
__device__ __forceinline__ void tma_3d(uint32_t dst, const CUtensorMap* m, int c0, int c1, int c2, uint32_t bar) {
  asm volatile("cp.async.bulk.tensor.3d.shared::cluster.global.mbarrier::complete_tx::bytes [%0], [%1, {%3, %4, %5}], [%2];" :: "r"(dst), "l"(m), "r"(bar), "r"(c0), "r"(c1), "r"(c2) : "memory");
}
__device__ __forceinline__ void tma_5d(uint32_t dst, const CUtensorMap* m, int c0, int c1, int c2, int c3, int c4, uint32_t bar) {
  asm volatile("cp.async.bulk.tensor.5d.shared::cluster.global.mbarrier::complete_tx::bytes [%0], [%1, {%3, %4, %5, %6, %7}], [%2];" :: "r"(dst), "l"(m), "r"(bar), "r"(c0), "r"(c1), "r"(c2), "r"(c3), "r"(c4) : "memory");
}
__device__ __forceinline__ void tma_store_3d(const CUtensorMap* m, int c0, int c1, int c2, uint32_t src) {
  asm volatile("cp.async.bulk.tensor.3d.global.shared::cta.bulk_group [%0, {%2, %3, %4}], [%1];" :: "l"(m), "r"(src), "r"(c0), "r"(c1), "r"(c2) : "memory");
}
__device__ __forceinline__ void tma_store_2d(const CUtensorMap* m, int c0, int c1, uint32_t src) {
  asm volatile("cp.async.bulk.tensor.2d.global.shared::cta.bulk_group [%0, {%2, %3}], [%1];" :: "l"(m), "r"(src), "r"(c0), "r"(c1) : "memory");
}
__device__ __forceinline__ void bulk_load(uint32_t dst, const void* src, uint32_t bytes, uint32_t bar) {
  asm volatile("cp.async.bulk.shared::cluster.global.mbarrier::complete_tx::bytes [%0], [%1], %2, [%3];" :: "r"(dst), "l"(src), "r"(bytes), "r"(bar) : "memory");
}
__device__ __forceinline__ void prefetch_map(const CUtensorMap* m) { asm volatile("prefetch.tensormap [%0];" :: "l"(m) : "memory"); }
__device__ __forceinline__ void wgmma_fence() { asm volatile("wgmma.fence.sync.aligned;" ::: "memory"); }
__device__ __forceinline__ void wgmma_commit() { asm volatile("wgmma.commit_group.sync.aligned;" ::: "memory"); }
template <int N> __device__ __forceinline__ void wgmma_wait() { asm volatile("wgmma.wait_group.sync.aligned %0;" :: "n"(N) : "memory"); }
__device__ __forceinline__ uint32_t desc_lo(uint32_t addr, uint32_t lbo) { return ((addr & 0x3FFFF) >> 4) | ((lbo >> 4) << 16); }
constexpr uint32_t desc_hi(uint32_t sbo, uint32_t swz) { return (sbo >> 4) | (swz << 30); }
constexpr uint32_t HI_SW128 = desc_hi(1024, 1), HI_SW64 = desc_hi(512, 2), HI_CONV_A = desc_hi(TAB_P, 0), HI_CONV_B = desc_hi(128, 0), HI_BLK = desc_hi(1024, 0);
template <int R> __device__ __forceinline__ void reg_inc() { asm volatile("setmaxnreg.inc.sync.aligned.u32 %0;" :: "n"(R)); }
template <int R> __device__ __forceinline__ void reg_dec() { asm volatile("setmaxnreg.dec.sync.aligned.u32 %0;" :: "n"(R)); }
__device__ __forceinline__ uint32_t pack_bf16(float lo, float hi) { uint32_t r; asm("cvt.rn.bf16x2.f32 %0, %1, %2;" : "=r"(r) : "f"(hi), "f"(lo)); return r; }
__device__ __forceinline__ float bf_lo(uint32_t v) { return __uint_as_float(v << 16); }
__device__ __forceinline__ float bf_hi(uint32_t v) { return __uint_as_float(v & 0xFFFF0000u); }
__device__ __forceinline__ float bf_round(float x) { return bf_lo(pack_bf16(x, 0.f) & 0xFFFFu); }
__device__ __forceinline__ uint32_t bmul2(uint32_t a, uint32_t b) { uint32_t r; asm("mul.rn.bf16x2 %0, %1, %2;" : "=r"(r) : "r"(a), "r"(b)); return r; }
__device__ __forceinline__ uint32_t badd2(uint32_t a, uint32_t b) { uint32_t r; asm("add.rn.bf16x2 %0, %1, %2;" : "=r"(r) : "r"(a), "r"(b)); return r; }
__device__ __forceinline__ uint32_t bsub2(uint32_t a, uint32_t b) { uint32_t r; asm("sub.rn.bf16x2 %0, %1, %2;" : "=r"(r) : "r"(a), "r"(b)); return r; }
__device__ __forceinline__ uint4 ldg128(const void* p) { uint4 v; asm volatile("ld.global.nc.L1::no_allocate.v4.u32 {%0,%1,%2,%3}, [%4];" : "=r"(v.x), "=r"(v.y), "=r"(v.z), "=r"(v.w) : "l"(p)); return v; }
__device__ __forceinline__ uint2 ldg64(const void* p) { uint2 v; asm volatile("ld.global.nc.L1::no_allocate.v2.u32 {%0,%1}, [%2];" : "=r"(v.x), "=r"(v.y) : "l"(p)); return v; }
__device__ __forceinline__ void stg128(void* p, uint32_t a, uint32_t b, uint32_t c, uint32_t d) { asm volatile("st.global.v4.u32 [%0], {%1,%2,%3,%4};" :: "l"(p), "r"(a), "r"(b), "r"(c), "r"(d) : "memory"); }
__device__ __forceinline__ void sts128(uint32_t a, uint32_t x, uint32_t y, uint32_t z, uint32_t w) { asm volatile("st.shared.v4.u32 [%0], {%1,%2,%3,%4};" :: "r"(a), "r"(x), "r"(y), "r"(z), "r"(w) : "memory"); }
__device__ __forceinline__ void sts32(uint32_t a, uint32_t x) { asm volatile("st.shared.u32 [%0], %1;" :: "r"(a), "r"(x) : "memory"); }
__device__ __forceinline__ uint32_t lds32(uint32_t a) { uint32_t v; asm volatile("ld.shared.u32 %0, [%1];" : "=r"(v) : "r"(a) : "memory"); return v; }
__device__ __forceinline__ float2 lds64f(uint32_t a) { float2 v; asm volatile("ld.shared.v2.f32 {%0,%1}, [%2];" : "=f"(v.x), "=f"(v.y) : "r"(a) : "memory"); return v; }
__device__ __forceinline__ void ldmatrix_x4_t(uint32_t a, uint32_t& r0, uint32_t& r1, uint32_t& r2, uint32_t& r3) {
  asm volatile("ldmatrix.sync.aligned.m8n8.x4.trans.shared.b16 {%0,%1,%2,%3}, [%4];" : "=r"(r0), "=r"(r1), "=r"(r2), "=r"(r3) : "r"(a) : "memory");
}

__device__ __forceinline__ void stmatrix_x4_t(uint32_t a, uint32_t r0, uint32_t r1, uint32_t r2, uint32_t r3) {
  asm volatile("stmatrix.sync.aligned.m8n8.x4.trans.shared.b16 [%0], {%1,%2,%3,%4};" :: "r"(a), "r"(r0), "r"(r1), "r"(r2), "r"(r3) : "memory");
}

__device__ __forceinline__ uint32_t ldg32(const void* p) { uint32_t v; asm volatile("ld.global.nc.L1::no_allocate.u32 %0, [%1];" : "=r"(v) : "l"(p)); return v; }
__device__ __forceinline__ uint4 lds128(uint32_t a) { uint4 v; asm volatile("ld.shared.v4.u32 {%0,%1,%2,%3}, [%4];" : "=r"(v.x), "=r"(v.y), "=r"(v.z), "=r"(v.w) : "r"(a) : "memory"); return v; }

template <uint32_t AHI, uint32_t BHI, int AOFF, int BOFF>
__device__ __forceinline__ void wgmma_n64_t01(float* d, uint32_t alo, uint32_t blo, int sd) {
  asm volatile("{\n.reg .pred p;\n.reg .b32 ta, tb;\n.reg .b64 da, db;\nsetp.ne.b32 p, %34, 0;\nadd.u32 ta, %32, %37;\nadd.u32 tb, %33, %38;\nmov.b64 da, {ta, %35};\nmov.b64 db, {tb, %36};\nwgmma.mma_async.sync.aligned.m64n64k16.f32.bf16.bf16 {%0, %1, %2, %3, %4, %5, %6, %7, %8, %9, %10, %11, %12, %13, %14, %15, %16, %17, %18, %19, %20, %21, %22, %23, %24, %25, %26, %27, %28, %29, %30, %31}, da, db, p, 1, 1, 0, 1;\n}\n"
    : "+f"(d[0]), "+f"(d[1]), "+f"(d[2]), "+f"(d[3]), "+f"(d[4]), "+f"(d[5]), "+f"(d[6]), "+f"(d[7]), "+f"(d[8]), "+f"(d[9]), "+f"(d[10]), "+f"(d[11]), "+f"(d[12]), "+f"(d[13]), "+f"(d[14]), "+f"(d[15]), "+f"(d[16]), "+f"(d[17]), "+f"(d[18]), "+f"(d[19]), "+f"(d[20]), "+f"(d[21]), "+f"(d[22]), "+f"(d[23]), "+f"(d[24]), "+f"(d[25]), "+f"(d[26]), "+f"(d[27]), "+f"(d[28]), "+f"(d[29]), "+f"(d[30]), "+f"(d[31])
    : "r"(alo), "r"(blo), "r"(sd), "n"(AHI), "n"(BHI), "n"(AOFF), "n"(BOFF));
}
template <uint32_t AHI, uint32_t BHI, int AOFF, int BOFF>
__device__ __forceinline__ void wgmma_n128_t01(float* d, uint32_t alo, uint32_t blo, int sd) {
  asm volatile("{\n.reg .pred p;\n.reg .b32 ta, tb;\n.reg .b64 da, db;\nsetp.ne.b32 p, %66, 0;\nadd.u32 ta, %64, %69;\nadd.u32 tb, %65, %70;\nmov.b64 da, {ta, %67};\nmov.b64 db, {tb, %68};\nwgmma.mma_async.sync.aligned.m64n128k16.f32.bf16.bf16 {%0, %1, %2, %3, %4, %5, %6, %7, %8, %9, %10, %11, %12, %13, %14, %15, %16, %17, %18, %19, %20, %21, %22, %23, %24, %25, %26, %27, %28, %29, %30, %31, %32, %33, %34, %35, %36, %37, %38, %39, %40, %41, %42, %43, %44, %45, %46, %47, %48, %49, %50, %51, %52, %53, %54, %55, %56, %57, %58, %59, %60, %61, %62, %63}, da, db, p, 1, 1, 0, 1;\n}\n"
    : "+f"(d[0]), "+f"(d[1]), "+f"(d[2]), "+f"(d[3]), "+f"(d[4]), "+f"(d[5]), "+f"(d[6]), "+f"(d[7]), "+f"(d[8]), "+f"(d[9]), "+f"(d[10]), "+f"(d[11]), "+f"(d[12]), "+f"(d[13]), "+f"(d[14]), "+f"(d[15]), "+f"(d[16]), "+f"(d[17]), "+f"(d[18]), "+f"(d[19]), "+f"(d[20]), "+f"(d[21]), "+f"(d[22]), "+f"(d[23]), "+f"(d[24]), "+f"(d[25]), "+f"(d[26]), "+f"(d[27]), "+f"(d[28]), "+f"(d[29]), "+f"(d[30]), "+f"(d[31]), "+f"(d[32]), "+f"(d[33]), "+f"(d[34]), "+f"(d[35]), "+f"(d[36]), "+f"(d[37]), "+f"(d[38]), "+f"(d[39]), "+f"(d[40]), "+f"(d[41]), "+f"(d[42]), "+f"(d[43]), "+f"(d[44]), "+f"(d[45]), "+f"(d[46]), "+f"(d[47]), "+f"(d[48]), "+f"(d[49]), "+f"(d[50]), "+f"(d[51]), "+f"(d[52]), "+f"(d[53]), "+f"(d[54]), "+f"(d[55]), "+f"(d[56]), "+f"(d[57]), "+f"(d[58]), "+f"(d[59]), "+f"(d[60]), "+f"(d[61]), "+f"(d[62]), "+f"(d[63])
    : "r"(alo), "r"(blo), "r"(sd), "n"(AHI), "n"(BHI), "n"(AOFF), "n"(BOFF));
}
template <uint32_t AHI, uint32_t BHI, int AOFF, int BOFF>
__device__ __forceinline__ void wgmma_n128_t10(float* d, uint32_t alo, uint32_t blo, int sd) {
  asm volatile("{\n.reg .pred p;\n.reg .b32 ta, tb;\n.reg .b64 da, db;\nsetp.ne.b32 p, %66, 0;\nadd.u32 ta, %64, %69;\nadd.u32 tb, %65, %70;\nmov.b64 da, {ta, %67};\nmov.b64 db, {tb, %68};\nwgmma.mma_async.sync.aligned.m64n128k16.f32.bf16.bf16 {%0, %1, %2, %3, %4, %5, %6, %7, %8, %9, %10, %11, %12, %13, %14, %15, %16, %17, %18, %19, %20, %21, %22, %23, %24, %25, %26, %27, %28, %29, %30, %31, %32, %33, %34, %35, %36, %37, %38, %39, %40, %41, %42, %43, %44, %45, %46, %47, %48, %49, %50, %51, %52, %53, %54, %55, %56, %57, %58, %59, %60, %61, %62, %63}, da, db, p, 1, 1, 1, 0;\n}\n"
    : "+f"(d[0]), "+f"(d[1]), "+f"(d[2]), "+f"(d[3]), "+f"(d[4]), "+f"(d[5]), "+f"(d[6]), "+f"(d[7]), "+f"(d[8]), "+f"(d[9]), "+f"(d[10]), "+f"(d[11]), "+f"(d[12]), "+f"(d[13]), "+f"(d[14]), "+f"(d[15]), "+f"(d[16]), "+f"(d[17]), "+f"(d[18]), "+f"(d[19]), "+f"(d[20]), "+f"(d[21]), "+f"(d[22]), "+f"(d[23]), "+f"(d[24]), "+f"(d[25]), "+f"(d[26]), "+f"(d[27]), "+f"(d[28]), "+f"(d[29]), "+f"(d[30]), "+f"(d[31]), "+f"(d[32]), "+f"(d[33]), "+f"(d[34]), "+f"(d[35]), "+f"(d[36]), "+f"(d[37]), "+f"(d[38]), "+f"(d[39]), "+f"(d[40]), "+f"(d[41]), "+f"(d[42]), "+f"(d[43]), "+f"(d[44]), "+f"(d[45]), "+f"(d[46]), "+f"(d[47]), "+f"(d[48]), "+f"(d[49]), "+f"(d[50]), "+f"(d[51]), "+f"(d[52]), "+f"(d[53]), "+f"(d[54]), "+f"(d[55]), "+f"(d[56]), "+f"(d[57]), "+f"(d[58]), "+f"(d[59]), "+f"(d[60]), "+f"(d[61]), "+f"(d[62]), "+f"(d[63])
    : "r"(alo), "r"(blo), "r"(sd), "n"(AHI), "n"(BHI), "n"(AOFF), "n"(BOFF));
}
template <uint32_t AHI, uint32_t BHI, int AOFF, int BOFF>
__device__ __forceinline__ void wgmma_n8_t10(float* d, uint32_t alo, uint32_t blo, int sd) {
  asm volatile("{\n.reg .pred p;\n.reg .b32 ta, tb;\n.reg .b64 da, db;\nsetp.ne.b32 p, %6, 0;\nadd.u32 ta, %4, %9;\nadd.u32 tb, %5, %10;\nmov.b64 da, {ta, %7};\nmov.b64 db, {tb, %8};\nwgmma.mma_async.sync.aligned.m64n8k16.f32.bf16.bf16 {%0, %1, %2, %3}, da, db, p, 1, 1, 1, 0;\n}\n"
    : "+f"(d[0]), "+f"(d[1]), "+f"(d[2]), "+f"(d[3])
    : "r"(alo), "r"(blo), "r"(sd), "n"(AHI), "n"(BHI), "n"(AOFF), "n"(BOFF));
}
template <uint32_t AHI, uint32_t BHI, int AOFF, int BOFF>
__device__ __forceinline__ void wgmma_n128_t00(float* d, uint32_t alo, uint32_t blo, int sd) {
  asm volatile("{\n.reg .pred p;\n.reg .b32 ta, tb;\n.reg .b64 da, db;\nsetp.ne.b32 p, %66, 0;\nadd.u32 ta, %64, %69;\nadd.u32 tb, %65, %70;\nmov.b64 da, {ta, %67};\nmov.b64 db, {tb, %68};\nwgmma.mma_async.sync.aligned.m64n128k16.f32.bf16.bf16 {%0, %1, %2, %3, %4, %5, %6, %7, %8, %9, %10, %11, %12, %13, %14, %15, %16, %17, %18, %19, %20, %21, %22, %23, %24, %25, %26, %27, %28, %29, %30, %31, %32, %33, %34, %35, %36, %37, %38, %39, %40, %41, %42, %43, %44, %45, %46, %47, %48, %49, %50, %51, %52, %53, %54, %55, %56, %57, %58, %59, %60, %61, %62, %63}, da, db, p, 1, 1, 0, 0;\n}\n"
    : "+f"(d[0]), "+f"(d[1]), "+f"(d[2]), "+f"(d[3]), "+f"(d[4]), "+f"(d[5]), "+f"(d[6]), "+f"(d[7]), "+f"(d[8]), "+f"(d[9]), "+f"(d[10]), "+f"(d[11]), "+f"(d[12]), "+f"(d[13]), "+f"(d[14]), "+f"(d[15]), "+f"(d[16]), "+f"(d[17]), "+f"(d[18]), "+f"(d[19]), "+f"(d[20]), "+f"(d[21]), "+f"(d[22]), "+f"(d[23]), "+f"(d[24]), "+f"(d[25]), "+f"(d[26]), "+f"(d[27]), "+f"(d[28]), "+f"(d[29]), "+f"(d[30]), "+f"(d[31]), "+f"(d[32]), "+f"(d[33]), "+f"(d[34]), "+f"(d[35]), "+f"(d[36]), "+f"(d[37]), "+f"(d[38]), "+f"(d[39]), "+f"(d[40]), "+f"(d[41]), "+f"(d[42]), "+f"(d[43]), "+f"(d[44]), "+f"(d[45]), "+f"(d[46]), "+f"(d[47]), "+f"(d[48]), "+f"(d[49]), "+f"(d[50]), "+f"(d[51]), "+f"(d[52]), "+f"(d[53]), "+f"(d[54]), "+f"(d[55]), "+f"(d[56]), "+f"(d[57]), "+f"(d[58]), "+f"(d[59]), "+f"(d[60]), "+f"(d[61]), "+f"(d[62]), "+f"(d[63])
    : "r"(alo), "r"(blo), "r"(sd), "n"(AHI), "n"(BHI), "n"(AOFF), "n"(BOFF));
}
template <uint32_t AHI, uint32_t BHI, int AOFF, int BOFF>
__device__ __forceinline__ void wgmma_n96_t00(float* d, uint32_t alo, uint32_t blo, int sd) {
  asm volatile("{\n.reg .pred p;\n.reg .b32 ta, tb;\n.reg .b64 da, db;\nsetp.ne.b32 p, %50, 0;\nadd.u32 ta, %48, %53;\nadd.u32 tb, %49, %54;\nmov.b64 da, {ta, %51};\nmov.b64 db, {tb, %52};\nwgmma.mma_async.sync.aligned.m64n96k16.f32.bf16.bf16 {%0, %1, %2, %3, %4, %5, %6, %7, %8, %9, %10, %11, %12, %13, %14, %15, %16, %17, %18, %19, %20, %21, %22, %23, %24, %25, %26, %27, %28, %29, %30, %31, %32, %33, %34, %35, %36, %37, %38, %39, %40, %41, %42, %43, %44, %45, %46, %47}, da, db, p, 1, 1, 0, 0;\n}\n"
    : "+f"(d[0]), "+f"(d[1]), "+f"(d[2]), "+f"(d[3]), "+f"(d[4]), "+f"(d[5]), "+f"(d[6]), "+f"(d[7]), "+f"(d[8]), "+f"(d[9]), "+f"(d[10]), "+f"(d[11]), "+f"(d[12]), "+f"(d[13]), "+f"(d[14]), "+f"(d[15]), "+f"(d[16]), "+f"(d[17]), "+f"(d[18]), "+f"(d[19]), "+f"(d[20]), "+f"(d[21]), "+f"(d[22]), "+f"(d[23]), "+f"(d[24]), "+f"(d[25]), "+f"(d[26]), "+f"(d[27]), "+f"(d[28]), "+f"(d[29]), "+f"(d[30]), "+f"(d[31]), "+f"(d[32]), "+f"(d[33]), "+f"(d[34]), "+f"(d[35]), "+f"(d[36]), "+f"(d[37]), "+f"(d[38]), "+f"(d[39]), "+f"(d[40]), "+f"(d[41]), "+f"(d[42]), "+f"(d[43]), "+f"(d[44]), "+f"(d[45]), "+f"(d[46]), "+f"(d[47])
    : "r"(alo), "r"(blo), "r"(sd), "n"(AHI), "n"(BHI), "n"(AOFF), "n"(BOFF));
}
template <uint32_t AHI, uint32_t BHI, int AOFF, int BOFF>
__device__ __forceinline__ void wgmma_n64_t00(float* d, uint32_t alo, uint32_t blo, int sd) {
  asm volatile("{\n.reg .pred p;\n.reg .b32 ta, tb;\n.reg .b64 da, db;\nsetp.ne.b32 p, %34, 0;\nadd.u32 ta, %32, %37;\nadd.u32 tb, %33, %38;\nmov.b64 da, {ta, %35};\nmov.b64 db, {tb, %36};\nwgmma.mma_async.sync.aligned.m64n64k16.f32.bf16.bf16 {%0, %1, %2, %3, %4, %5, %6, %7, %8, %9, %10, %11, %12, %13, %14, %15, %16, %17, %18, %19, %20, %21, %22, %23, %24, %25, %26, %27, %28, %29, %30, %31}, da, db, p, 1, 1, 0, 0;\n}\n"
    : "+f"(d[0]), "+f"(d[1]), "+f"(d[2]), "+f"(d[3]), "+f"(d[4]), "+f"(d[5]), "+f"(d[6]), "+f"(d[7]), "+f"(d[8]), "+f"(d[9]), "+f"(d[10]), "+f"(d[11]), "+f"(d[12]), "+f"(d[13]), "+f"(d[14]), "+f"(d[15]), "+f"(d[16]), "+f"(d[17]), "+f"(d[18]), "+f"(d[19]), "+f"(d[20]), "+f"(d[21]), "+f"(d[22]), "+f"(d[23]), "+f"(d[24]), "+f"(d[25]), "+f"(d[26]), "+f"(d[27]), "+f"(d[28]), "+f"(d[29]), "+f"(d[30]), "+f"(d[31])
    : "r"(alo), "r"(blo), "r"(sd), "n"(AHI), "n"(BHI), "n"(AOFF), "n"(BOFF));
}
template <uint32_t AHI, uint32_t BHI, int AOFF, int BOFF>
__device__ __forceinline__ void wgmma_n32_t00(float* d, uint32_t alo, uint32_t blo, int sd) {
  asm volatile("{\n.reg .pred p;\n.reg .b32 ta, tb;\n.reg .b64 da, db;\nsetp.ne.b32 p, %18, 0;\nadd.u32 ta, %16, %21;\nadd.u32 tb, %17, %22;\nmov.b64 da, {ta, %19};\nmov.b64 db, {tb, %20};\nwgmma.mma_async.sync.aligned.m64n32k16.f32.bf16.bf16 {%0, %1, %2, %3, %4, %5, %6, %7, %8, %9, %10, %11, %12, %13, %14, %15}, da, db, p, 1, 1, 0, 0;\n}\n"
    : "+f"(d[0]), "+f"(d[1]), "+f"(d[2]), "+f"(d[3]), "+f"(d[4]), "+f"(d[5]), "+f"(d[6]), "+f"(d[7]), "+f"(d[8]), "+f"(d[9]), "+f"(d[10]), "+f"(d[11]), "+f"(d[12]), "+f"(d[13]), "+f"(d[14]), "+f"(d[15])
    : "r"(alo), "r"(blo), "r"(sd), "n"(AHI), "n"(BHI), "n"(AOFF), "n"(BOFF));
}
template <int N, uint32_t AHI, uint32_t BHI, int AOFF, int BOFF> __device__ __forceinline__ void wgmma_conv(float* d, uint32_t alo, uint32_t blo, int sd) {
  if constexpr (N == 128) wgmma_n128_t00<AHI, BHI, AOFF, BOFF>(d, alo, blo, sd);
  if constexpr (N == 96) wgmma_n96_t00<AHI, BHI, AOFF, BOFF>(d, alo, blo, sd);
  if constexpr (N == 64) wgmma_n64_t00<AHI, BHI, AOFF, BOFF>(d, alo, blo, sd);
  if constexpr (N == 32) wgmma_n32_t00<AHI, BHI, AOFF, BOFF>(d, alo, blo, sd);
}

template <int Q>
__device__ __forceinline__ void h_epilogue(const float* G, const float* U, float4* c, float4 s, __nv_bfloat16* p, uint32_t* H, uint32_t next) {
  uint32_t h1[2], h2[2];
#pragma unroll
  for (int q = 0; q < 2; q++) {
    const int j = 2 * Q + q;
    h1[q] = pack_bf16(fmaf(-s.x, c[q].x, G[4 * j]) * fmaf(-s.x, c[q].z, U[4 * j]) * s.y, fmaf(-s.x, c[q].y, G[4 * j + 1]) * fmaf(-s.x, c[q].w, U[4 * j + 1]) * s.y);
    h2[q] = pack_bf16(fmaf(-s.z, c[q].x, G[4 * j + 2]) * fmaf(-s.z, c[q].z, U[4 * j + 2]) * s.w, fmaf(-s.z, c[q].y, G[4 * j + 3]) * fmaf(-s.z, c[q].w, U[4 * j + 3]) * s.w);
  }
  if (next) { c[0] = lds128f(next); c[1] = lds128f(next + 64); }
  if (Q == 0) { H[0] = h1[0]; H[1] = h1[1]; H[2] = h2[0]; H[3] = h2[1]; }
  else {
    stg128(p, H[0], H[1], h1[0], h1[1]);
    stg128(p + 512, H[2], H[3], h2[0], h2[1]);
  }
}

template <int C>
__device__ __forceinline__ void conv_group(float* d, uint32_t alo, uint32_t blo) {
  constexpr int N = 128 - 32 * (C >> 1);
  constexpr int R0 = 24 - 16 * (C & 1);
  constexpr uint32_t AHI = HI_CONV_A, BHI = HI_CONV_B;
  wgmma_conv<N, AHI, BHI, 0, R0>(d, alo, blo, C == 0 ? 0 : 1);
  wgmma_conv<N, AHI, BHI, 8 * TAB_P / 16, R0 - 2>(d, alo, blo, 1);
  wgmma_conv<N, AHI, BHI, 16 * TAB_P / 16, R0 - 4>(d, alo, blo, 1);
  wgmma_conv<N, AHI, BHI, 24 * TAB_P / 16, R0 - 6>(d, alo, blo, 1);
}
template <int NR> __device__ __forceinline__ void copy_regs(float* dst, const float* src) {
#pragma unroll
  for (int i = 0; i < NR; i++) asm volatile("mov.b32 %0, %1;" : "=f"(dst[i]) : "f"(src[i]));
}

struct TabRegs { uint4 a, c; uint32_t x[5]; };
__device__ __forceinline__ void tab_load(TabRegs& T, uint32_t hk, int w, int lane) {
  const int v = ((lane >> 1) + 4 * (lane & 1)) & 15;
  const uint32_t src = hk + (32 * (w >> 1) + v + 16 * (lane & 1)) * 16;
  T.a = lds128(src); T.c = lds128(src + 16);
  if (w == 0) {
    const uint32_t s2 = hk + (32 * (lane >> 4) + 16 + 16 * ((lane >> 3) & 1)) * 16 + ((8 - (lane & 7)) >> 1) * 4;
#pragma unroll
    for (int i = 0; i < 5; i++) T.x[i] = lds32(s2 + 4 * i);
  }
}
__device__ __forceinline__ void tab_store(const TabRegs& T, uint32_t tab, int w, int lane) {
  const uint32_t dst = tab + (w >> 1) * TAB_BUF + ((lane + 8 * (lane & 1)) & 31) * TAB_P;
  const uint4 a = T.a, c = T.c;
  if ((w & 1) == 0) {
    sts128(dst + 0, c.x, c.y, c.z, c.w);
    sts128(dst + 32, a.w, c.x, c.y, c.z);
    sts128(dst + 64, a.z, a.w, c.x, c.y);
    sts128(dst + 96, a.y, a.z, a.w, c.x);
    if (w == 0) {
      const uint32_t sel = (lane & 1) ? 0x5432 : 0x3210;
      sts128(tab + (lane >> 4) * TAB_BUF + (32 + ((lane >> 3) & 1)) * TAB_P + (lane & 7) * 16,
             __byte_perm(T.x[0], T.x[1], sel), __byte_perm(T.x[1], T.x[2], sel), __byte_perm(T.x[2], T.x[3], sel), __byte_perm(T.x[3], T.x[4], sel));
    }
  } else {
    const uint32_t o0 = __byte_perm(a.x, a.y, 0x5432), o1 = __byte_perm(a.y, a.z, 0x5432), o2 = __byte_perm(a.z, a.w, 0x5432),
                   o3 = __byte_perm(a.w, c.x, 0x5432), o4 = __byte_perm(c.x, c.y, 0x5432), o5 = __byte_perm(c.y, c.z, 0x5432),
                   o6 = __byte_perm(c.z, c.w, 0x5432);
    sts128(dst + 16, o3, o4, o5, o6);
    sts128(dst + 48, o2, o3, o4, o5);
    sts128(dst + 80, o1, o2, o3, o4);
    sts128(dst + 112, o0, o1, o2, o3);
  }
}
__device__ __forceinline__ void conv_pre(uint32_t cv, uint32_t hk) {
  const int t128 = fresh_tid() & 127, lane = t128 & 31, w = __shfl_sync(0xffffffffu, t128 >> 5, 0);
  TabRegs T;
  tab_load(T, hk, w, lane);
  tab_store(T, cv + CV_TAB, w, lane);
}

template <typename F>
__device__ __forceinline__ void conv_one(int chg, uint32_t cv, uint32_t hk, int nb0, uint32_t DD, bool first, uint32_t pbar, F&& mid) {
  const int t128 = fresh_tid() & 127, lane = t128 & 31, w = __shfl_sync(0xffffffffu, t128 >> 5, 0), g = lane >> 2, t = lane & 3;
  const uint32_t kvlo = desc_lo(cv, KV_HALF), tablo = desc_lo(cv + CV_TAB, 2 * TAB_P);
  TabRegs T;
  auto eload = [&](int k) { tab_load(T, hk + (k < 4 ? k * 1024 : CV_HBUF), w, lane); };
  auto estore = [&](int k) { tab_store(T, cv + CV_TAB + (k & 1) * 2 * TAB_BUF, w, lane); };
  eload(1);
  float d[64];
  {
    float d0[64], d1[48], d2[32], d3[16];
#define CONV_STEP(K, DC) { \
    fence_async_smem(); \
    named_bar_r(nb0, 128); \
    if ((K) < 3 || first) { estore((K) + 1); if ((K) < 2 || ((K) == 2 && first)) eload((K) + 2); } \
    mid(std::integral_constant<int, K>{}); \
    wgmma_fence(); \
    conv_group<2 * (K)>(DC, tablo + ((K) & 1) * (2 * TAB_BUF / 16), kvlo); \
    conv_group<2 * (K) + 1>(DC, tablo + (((K) & 1) * 2 + 1) * (TAB_BUF / 16), kvlo); \
    wgmma_commit(); \
    wgmma_wait<0>(); }
    CONV_STEP(0, d0) copy_regs<48>(d1, d0 + 16);
    CONV_STEP(1, d1) copy_regs<32>(d2, d1 + 16);
    CONV_STEP(2, d2) copy_regs<16>(d3, d2 + 16);
    CONV_STEP(3, d3)
#pragma unroll
    for (int i = 0; i < 16; i++) { d[i] = d0[i]; d[16 + i] = d1[i]; d[32 + i] = d2[i]; d[48 + i] = d3[i]; }
  }
  if (t128 < 2) mbar_arrive(pbar);
#pragma unroll
  for (int j = 15; j >= 1; j--) { d[4 * j] += d[4 * (j - 1) + 2]; d[4 * j + 1] += d[4 * (j - 1) + 3]; }
  uint32_t kd[16];
  named_bar_r(nb0, 128);
  if (w >= 2) {
    const uint32_t ra = cv + CV_RED + (w - 2) * 4096 + 2048 + lane * 16;
    const uint32_t rb = cv + CV_RED + (w - 2) * 4096 + ((lane & 28) | ((t + 1) & 3)) * 16;
#pragma unroll
    for (int q = 0; q < 4; q++) {
      sts128(ra + q * 512, __float_as_uint(d[16 * q]), __float_as_uint(d[16 * q + 4]), __float_as_uint(d[16 * q + 8]), __float_as_uint(d[16 * q + 12]));
      float f[4];
#pragma unroll
      for (int i = 0; i < 4; i++) { const int j = 4 * q + i; f[i] = (t == 3) ? (j > 0 ? d[4 * (j - 1) + 1] : 0.f) : d[4 * j + 1]; }
      sts128(rb + q * 512, __float_as_uint(f[0]), __float_as_uint(f[1]), __float_as_uint(f[2]), __float_as_uint(f[3]));
    }
  } else {
    const uint32_t ka = cv + (1 - w) * KV_HALF + KV_PAD + lane * 16;
#pragma unroll
    for (int q = 0; q < 4; q++) ldmatrix_x4_t(ka + q * 512, kd[4 * q], kd[4 * q + 1], kd[4 * q + 2], kd[4 * q + 3]);
  }
  named_bar_r(nb0, 128);
  if (w < 2) {
    const uint32_t ra = cv + CV_RED + w * 4096 + lane * 16;
    const uint32_t zs = hk + 32 + (4 * (8 * w + 7 - g) + t) * 4;
#pragma unroll
    for (int q = 0; q < 4; q++) {
      const float4 p0 = lds128f(ra + q * 512), p1 = lds128f(ra + 2048 + q * 512);
      d[16 * q] += p0.x; d[16 * q + 1] += p1.x; d[16 * q + 4] += p0.y; d[16 * q + 5] += p1.y;
      d[16 * q + 8] += p0.z; d[16 * q + 9] += p1.z; d[16 * q + 12] += p0.w; d[16 * q + 13] += p1.w;
    }
#pragma unroll
    for (int q = 0; q < 16; q++) sts32(zs + 256 * q, badd2(pack_bf16(d[4 * q], d[4 * q + 1]), bmul2(kd[q], DD)));
    fence_async_smem();
    named_arrive_r(nb0 + 1, 96);
  } else if (w == 3) {
    named_bar_r(nb0 + 1, 96);
    if (lane == 0) bulk_store(g_zT + (size_t)chg * SEQ, hk + 32, 4096);
    __syncwarp();
  }
}

__global__ void __launch_bounds__(512, 1) fused_kernel(const __grid_constant__ Maps maps, const Ptrs P) {
  extern __shared__ __align__(1024) uint8_t smem[];
  const uint32_t sb = smem_u32(smem);
  const uint32_t bars = sb + SM_BAR;
  const int warp = __shfl_sync(0xffffffffu, (int)threadIdx.x >> 5, 0), wg = warp >> 2;
  const int b = blockIdx.x;
  if (b >= NCTA) {
    const int tid = fresh_tid(), lane = tid & 31;
    if (warp < 12 && elect_one()) { mbar_init(bars + 8 * warp, 1); mbar_init(bars + 8 * (12 + warp), 4); }
    if (tid >= 64 && tid < 128) sts32(sb + 196608 + (tid - 64) * 4, 0x3F803F80u);
    fence_async_smem();
    __syncthreads();
    if (warp < 3) {
#pragma unroll 1
      for (int i = warp; i < 24; i += 3) {
        const int use = i / 12, slot = i - 12 * use;
        if (use > 0) mbar_wait(bars + 8 * (12 + slot), (use - 1) & 1);
        const int atom = 7 * (b - NCTA) + ((0x361 >> (4 * (i >> 3))) & 7);
        if (elect_one()) {
          mbar_expect_tx(bars + 8 * slot, 16384);
          tma_3d(sb + slot * 16384, &maps.w, atom * 64, (i & 7) * 64, 0, bars + 8 * slot);
        }
        __syncwarp();
      }
    } else if (wg == 1) {
      const unsigned tag = ld_relaxed(&g_cnt[C_DONE * 32]) / NCTA + 1;
      const uint32_t olo = desc_lo(sb + 196608, 128);
      int slot = 0, ph = 0;
#pragma unroll 1
      for (int q = 0; q < 3; q++) {
        float c0[4], c1[4];
#pragma unroll 1
        for (int i = 0; i < 8; i++) {
          mbar_wait_nt(bars + 8 * slot, ph);
          const uint32_t da = desc_lo(sb, 8192) + slot * 1024;
          wgmma_fence();
          wgmma_n8_t10<HI_SW128, HI_CONV_B, 0, 0>(c0, da, olo, i > 0);
          wgmma_n8_t10<HI_SW128, HI_CONV_B, 512, 0>(c1, da, olo, i > 0);
          wgmma_n8_t10<HI_SW128, HI_CONV_B, 128, 0>(c0, da, olo, 1);
          wgmma_n8_t10<HI_SW128, HI_CONV_B, 640, 0>(c1, da, olo, 1);
          wgmma_n8_t10<HI_SW128, HI_CONV_B, 256, 0>(c0, da, olo, 1);
          wgmma_n8_t10<HI_SW128, HI_CONV_B, 768, 0>(c1, da, olo, 1);
          wgmma_n8_t10<HI_SW128, HI_CONV_B, 384, 0>(c0, da, olo, 1);
          wgmma_n8_t10<HI_SW128, HI_CONV_B, 896, 0>(c1, da, olo, 1);
          wgmma_commit();
          wgmma_wait<0>();
          if (lane == 0) mbar_arrive(bars + 8 * (12 + slot));
          if (++slot == 12) { slot = 0; ph ^= 1; }
        }
        if ((lane & 3) == 0) {
          const int atom = 7 * (b - NCTA) + ((0x361 >> (4 * q)) & 7);
          uint2* dst = reinterpret_cast<uint2*>(g_cs) + atom * 64 + 16 * (warp & 3) + (lane >> 2);
          st_relaxed64(dst, __float_as_uint(c0[0]), tag); st_relaxed64(dst + 8, __float_as_uint(c0[2]), tag);
          st_relaxed64(dst + FF, __float_as_uint(c1[0]), tag); st_relaxed64(dst + FF + 8, __float_as_uint(c1[2]), tag);
        }
      }
    }
    return;
  }
  int r, f, r2, nb;
  {
    const int c = b >> 1, side = b & 1, tp = c - 4;
    int grp, mem;
    if (c < 4) { grp = 15; mem = c; }
    else if (tp < 32) { grp = tp & 7; mem = tp >> 3; }
    else { grp = 8 + (tp - 32) % 7; mem = (tp - 32) / 7; }
    const int half = grp >= 8, sg = (grp == 15) ? 0 : (half ? grp - 7 : grp);
    r = 4 * (sg >> 1) + mem; f = 2 * (2 * (sg & 1) + half) + side;
    r2 = 4 * (sg >> 1) + 2 * half + (mem >> 1); nb = 4 * (sg & 1) + 2 * (mem & 1) + side;
  }
  const int pr = f >> 1, odd = f & 1;
  const int atomS = 7 * pr + 2 + 2 * odd, grpH = 14 * pr + 6 + odd;
  const int atom1 = 7 * pr + 5 * odd;
#define BAR(i) (bars + 8 * (i))

  if (elect_one()) {
    const uint32_t cnt = (0x22040801u >> (8 * ((BAR_CODES >> (2 * warp)) & 3))) & 0xFF;
#pragma unroll
    for (int q = 0; q < 4; q++) mbar_init(BAR(warp * 4 + q), cnt);
    fence_async_smem();
  }
  __syncthreads();
  auto sp0_load = [&](int st) {
    if (elect_one()) {
      mbar_expect_tx(BAR(B_XFULL + st), 32768);
      tma_3d(sb + SM_X + st * 16384, &maps.x, st * 64, 8 * r, 0, BAR(B_XFULL + st));
      tma_3d(sb + SM_RING + (st < 6 ? st : st - 6) * 16384, &maps.w, atom1 * 64, st * 64, 0, BAR(B_XFULL + st));
    }
    __syncwarp();
  };
  auto g2_load = [&](int i, unsigned epoch1) {
    const int use = i / G2_NB, buf = i - G2_NB * use;
    if (use == 0) mbar_wait(BAR(B_XFREE + (i < 2 ? 5 : 7)), 0);
    else mbar_wait(BAR(B_G2EMPTY + buf), (use - 1) & 1);
    if (i >= 8 && i < 11) mbar_wait(BAR(B_H1RDY), 0);
    if (i >= 16 && i < 19) mbar_wait(BAR(B_H1RDY + 1), 0);
    const int atom = c_atom[i];
    const uint32_t dst = sb + g2_off(buf);
    if (elect_one()) {
      mbar_expect_tx(BAR(B_G2FULL + buf), G2_STAGE);
      bulk_load(dst, g_h + (size_t)(r2 * 28 + atom) * 8192, 16384, BAR(B_G2FULL + buf));
      tma_5d(dst + 16384, &maps.wd, nb * 64, 0, 0, 0, atom * 2, BAR(B_G2FULL + buf));
    }
    __syncwarp();
  };
  if (warp == 0) {
#pragma unroll 1
    for (int st = 0; st < 6; st++) sp0_load(st);
  }

  if (wg == 0) {
    reg_dec<48>();
    const int tid = fresh_tid(), lane = tid & 31;
    if (warp == 0) {
      const unsigned done0 = ld_relaxed(&g_cnt[C_DONE * 32]);
      if (lane == 0) { prefetch_map(&maps.wd); prefetch_map(&maps.out); prefetch_map(&maps.z); prefetch_map(&maps.kv); }
#pragma unroll 1
      for (int st = 6; st < 28; st++) {
        const int slot = (st - 6) & 3;
        mbar_wait(BAR(B_WEMPTY + slot), ((st - 6) >> 2) & 1);
        if (st < 8) sp0_load(st);
        else {
          if (elect_one()) {
            const uint32_t dst = sb + SM_RING + slot * 16384;
            if (st < 24) { mbar_expect_tx(BAR(B_WFULL + slot), 16384); tma_3d(dst, &maps.w, (st < 16 ? atom1 + 1 : atomS) * 64, (st & 7) * 64, 0, BAR(B_WFULL + slot)); }
            else {
              mbar_expect_tx(BAR(B_WFULL + slot), 16384);
              tma_3d(dst, &maps.wh, grpH * 32, (st & 3) * 128, 0, BAR(B_WFULL + slot));
              tma_3d(dst + 8192, &maps.wh, grpH * 32, (st & 3) * 128 + 64, 0, BAR(B_WFULL + slot));
            }
          }
          __syncwarp();
        }
        if (st == 12) {
          const uint8_t* pw = reinterpret_cast<const uint8_t*>(P.wd) + (size_t)b * 14336 + lane * 128;
#pragma unroll
          for (int q = 0; q < 4; q++) if (q < 3 || lane < 16) asm volatile("prefetch.global.L2 [%0];" :: "l"(pw + q * 4096));
        }
      }
      const unsigned epoch1 = done0 / NCTA + 1;
      mbar_wait(BAR(B_H0RDY), 0);
#pragma unroll 1
      for (int i = 0; i < 28; i += 3) g2_load(i, epoch1);
    } else {
      const unsigned epoch1 = ld_relaxed(&g_cnt[C_DONE * 32]) / NCTA + 1;
      const int wi = warp - 1;
#pragma unroll 1
      for (int ph = 0; ph < 2; ph++) {
        const int k8 = b & 7, mat = (b >> 3) & 1, fo = b >> 4;
        const int atom = 7 * (fo >> 1) + (ph == 0 ? 5 * (fo & 1) : 2 + 2 * (fo & 1));
        const __nv_bfloat16* W = (mat ? P.w1 : P.w0) + atom * 64 + (lane & 7) * 8 + (size_t)(k8 * 64 + wi * 4 + (lane >> 3)) * FF;
        uint4 v[6];
#pragma unroll
        for (int i = 0; i < 6; i++) v[i] = (i < 5 || wi == 0) ? ldg128(W + (size_t)i * 12 * FF) : make_uint4(0, 0, 0, 0);
        float a[8];
#pragma unroll
        for (int i = 0; i < 8; i++) a[i] = 0.f;
#pragma unroll
        for (int i = 0; i < 6; i++) {
          a[0] += bf_lo(v[i].x); a[1] += bf_hi(v[i].x); a[2] += bf_lo(v[i].y); a[3] += bf_hi(v[i].y);
          a[4] += bf_lo(v[i].z); a[5] += bf_hi(v[i].z); a[6] += bf_lo(v[i].w); a[7] += bf_hi(v[i].w);
        }
#pragma unroll
        for (int i = 0; i < 8; i++) { a[i] += __shfl_xor_sync(0xffffffffu, a[i], 8); a[i] += __shfl_xor_sync(0xffffffffu, a[i], 16); }
        const uint32_t scr = sb + SM_CS + 1024 - ph * 768;
        if (lane < 8) {
          sts128(scr + wi * 256 + lane * 32, __float_as_uint(a[0]), __float_as_uint(a[1]), __float_as_uint(a[2]), __float_as_uint(a[3]));
          sts128(scr + wi * 256 + lane * 32 + 16, __float_as_uint(a[4]), __float_as_uint(a[5]), __float_as_uint(a[6]), __float_as_uint(a[7]));
        }
        named_bar<1, 96>();
        if (warp == 3) {
          const float2 p0 = lds64f(scr + lane * 8), p1 = lds64f(scr + 256 + lane * 8), p2 = lds64f(scr + 512 + lane * 8);
          st_relaxed128(&g_cs[(k8 * 2 + mat) * (FF / 2) + atom * 32 + lane], __float_as_uint(p0.x + p1.x + p2.x), epoch1, __float_as_uint(p0.y + p1.y + p2.y), epoch1);
        }
      }
      {
        float2 c = make_float2(0.f, 0.f);
        uint2 sv0, sv1;
        if (warp < 3) c = poll_cs8(wi, atom1 * 32 + lane, epoch1);
        else { sv0 = poll_stats(128 * r + 2 * lane, epoch1); sv1 = poll_stats(128 * r + 64 + 2 * lane, epoch1); }
        named_bar<1, 96>();
        if (warp < 3) sts64(sb + SM_CS + lane * 16 + wi * 8, c.x, c.y);
        else { sts64(sb + SM_ST + lane * 8, __uint_as_float(sv0.x), __uint_as_float(sv0.y)); sts64(sb + SM_ST + 256 + lane * 8, __uint_as_float(sv1.x), __uint_as_float(sv1.y)); }
        __syncwarp();
        if (lane == 0) { mbar_arrive(BAR(B_PREP)); if (warp == 1) mbar_arrive(BAR(B_PREP)); }
        if (warp < 3) {
          c = poll_cs8(wi, atomS * 32 + lane, epoch1);
          sts64(sb + SM_CS + (64 + lane) * 16 + wi * 8, c.x, c.y);
          __syncwarp();
          if (lane == 0) mbar_arrive(BAR(B_PREP2));
        }
      }
      if (warp == 3) {
        if (lane == 0) {
#pragma unroll 1
          for (int gq = 0; gq < 3; gq++) {
            mbar_wait(BAR(B_HDONE + gq), 0);
            red_release(&g_cnt[(C_H + 16 * gq + r) * 32]);
            spin_counter(&g_cnt[(C_H + 16 * gq + r2) * 32], epoch1 * 8);
            mbar_arrive(BAR(gq == 0 ? B_H0RDY : B_H1RDY + gq - 1));
            if (gq == 1) { mbar_wait(BAR(B_XFREE + 3), 0); mbar_expect_tx(BAR(B_FIN), 16384); tma_3d(sb + SM_FX, &maps.x, nb * 64, 8 * r2, 0, BAR(B_FIN)); }
          }
          spin_counter(&g_cnt[(C_Z + nb) * 32], epoch1 * 32);
          mbar_wait(BAR(B_AFREE), 0);
          mbar_expect_tx(BAR(B_FINZ), 16384);
          tma_2d(sb + SM_FZ, &maps.z, 128 * r2, 64 * nb, BAR(B_FINZ));
          tma_2d(sb + SM_FZ + 8192, &maps.z, 128 * r2 + 64, 64 * nb, BAR(B_FINZ));
        }
      } else {
        if (warp == 2) {
          uint4 c = poll_cs(atom1 * 32 + 32 + lane, epoch1);
          sts128(sb + SM_CS + (32 + lane) * 16, c.x, c.y, c.z, c.w);
          __syncwarp();
          if (lane == 0) mbar_arrive(BAR(B_PREP1));
          c = poll_cs(grpH * 16 + (lane & 15), epoch1);
          if (lane < 16) sts128(sb + SM_CS + (96 + lane) * 16, c.x, c.y, c.z, c.w);
          __syncwarp();
          if (lane == 0) { mbar_arrive(BAR(B_PREP2)); mbar_arrive(BAR(B_PREP2)); }
        }
        if (warp == 1) {
          const uint32_t cv = sb + SM_CVB, hbar = BAR(B_HKB);
          if (lane == 0) { spin_counter(&g_cnt[(C_KV + (b >> 5)) * 32], epoch1 * 32); mbar_arrive(BAR(B_KVRDY)); }
          __syncwarp();
          const uint4* kvsrc = g_kvT + (size_t)(4 * b + 2) * 256 + 2 * (lane & 15) + (lane >> 4);
          uint4 kq[8];
#pragma unroll
          for (int q = 0; q < 8; q++) kq[q] = ld_relaxed128(kvsrc + q * 32);
          mbar_wait(BAR(B_XFREE + 1), 0);
          if (lane == 0) {
            bulk_load(cv + CV_H + 32, P.ssm_k + (size_t)(4 * b + 2) * SEQ, 4096, hbar);
            bulk_load(cv + CV_H + CV_HBUF + 32, P.ssm_k + (size_t)(4 * b + 3) * SEQ, 4096, hbar);
          }
#pragma unroll
          for (int q = 0; q < 8; q++) sts128(cv + (lane >> 4) * KV_HALF + KV_PAD + (q * 16 + (lane & 15)) * 16, kq[q].x, kq[q].y, kq[q].z, kq[q].w);
          if (lane < 24) { sts128(cv + lane * 16, 0, 0, 0, 0); sts128(cv + KV_HALF + lane * 16, 0, 0, 0, 0); }
          else if (lane < 28) sts128(cv + CV_H + (lane & 1) * CV_HBUF + (lane & 2) * 8, 0, 0, 0, 0);
          __syncwarp();
          if (lane == 0) mbar_expect_tx(hbar, 8192);
        }
        uint2 fs0 = make_uint2(0, 0), fs1 = fs0;
        if (warp == 2) { fs0 = poll_stats(128 * r2 + 2 * lane, epoch1); fs1 = poll_stats(128 * r2 + 64 + 2 * lane, epoch1); }
        mbar_wait(BAR(B_H0RDY), 0);
#pragma unroll 1
        for (int i = warp; i < 28; i += 3) {
          g2_load(i, epoch1);
          if (i == 11) {
            mbar_wait(BAR(B_HDONE + 2), 0);
#pragma unroll
            for (int q = 0; q < 2; q++) {
              const int s2 = q * 32 + lane, m = 16 * (s2 & 7) + (s2 >> 3);
              const uint2 sv = q ? fs1 : fs0;
              sts64(sb + SM_CS + m * 8, bf_lo(sv.x), 1.f / bf_hi(sv.x)); sts64(sb + SM_CS + (m + 8) * 8, bf_lo(sv.y), 1.f / bf_hi(sv.y));
            }
            __syncwarp();
            if (lane == 0) mbar_arrive(BAR(B_ST2));
          }
        }
      }
    }
    return;
  } else if (wg == 3) {
    const int tid = fresh_tid(), lane = tid & 31;
    const int t128 = tid & 127, w = warp & 3;
    const unsigned tag = ld_relaxed(&g_cnt[C_DONE * 32]) / NCTA + 1;
    {
      const int row0 = 64 * (b >> 2), ch = 128 * (b & 3) + 4 * lane;
      uint4 xa[4], xb[4];
#pragma unroll
      for (int i = 0; i < 4; i++) {
        const __nv_bfloat16* row = P.x + (size_t)(16 * b + 4 * w + i) * DM;
        xa[i] = ldg128(row + lane * 8); xb[i] = ldg128(row + 256 + lane * 8);
      }
      uint2 kk[2][11], vv[2][8];
      auto load_round = [&](int rd) {
        const int rr = row0 + 8 * (4 * rd + w);
        const __nv_bfloat16* kp = P.k + (size_t)rr * DM + ch;
        const __nv_bfloat16* vp = P.v + (size_t)rr * DM + ch;
#pragma unroll
        for (int i = 0; i < 11; i++) kk[rd][i] = (i >= 3 || rr > 0) ? ldg64(kp + (i - 3) * DM) : make_uint2(0, 0);
#pragma unroll
        for (int i = 0; i < 8; i++) vv[rd][i] = ldg64(vp + i * DM);
      };
      const uint4 sa = ldg128(P.shift_k + ch * 4), sc = ldg128(P.shift_k + ch * 4 + 8);
      float2 res = make_float2(0.f, 0.f);
#pragma unroll
      for (int i = 0; i < 4; i++) {
        const uint32_t e[8] = {xa[i].x, xa[i].y, xa[i].z, xa[i].w, xb[i].x, xb[i].y, xb[i].z, xb[i].w};
        float s = 0.f;
#pragma unroll
        for (int q = 0; q < 8; q++) s += bf_lo(e[q]) + bf_hi(e[q]);
#pragma unroll
        for (int o = 16; o > 0; o >>= 1) s += __shfl_xor_sync(0xffffffffu, s, o);
        const float mu = s * (1.f / 512.f);
        float q2 = 0.f;
#pragma unroll
        for (int q = 0; q < 8; q++) { const float d0 = bf_lo(e[q]) - mu, d1 = bf_hi(e[q]) - mu; q2 = fmaf(d0, d0, q2); q2 = fmaf(d1, d1, q2); }
#pragma unroll
        for (int o = 16; o > 0; o >>= 1) q2 += __shfl_xor_sync(0xffffffffu, q2, o);
        if (lane == i) res = make_float2(mu, q2);
      }
      if (lane < 4) {
        const float var = bf_round(res.y * (1.f / 512.f));
        const float sd = bf_round(sqrtf(bf_round(var + 1e-5f)));
        st_relaxed64(&g_stats[16 * b + 4 * w + lane], pack_bf16(res.x, sd), tag);
      }
      mbar_wait(BAR(B_KVGATE), 0);
      load_round(0); load_round(1);
      uint32_t wA[4], wB[4];
      wA[0] = __byte_perm(sa.x, sa.z, 0x5410); wA[1] = __byte_perm(sa.x, sa.z, 0x7632); wA[2] = __byte_perm(sa.y, sa.w, 0x5410); wA[3] = __byte_perm(sa.y, sa.w, 0x7632);
      wB[0] = __byte_perm(sc.x, sc.z, 0x5410); wB[1] = __byte_perm(sc.x, sc.z, 0x7632); wB[2] = __byte_perm(sc.y, sc.w, 0x5410); wB[3] = __byte_perm(sc.y, sc.w, 0x7632);
#pragma unroll
      for (int rd = 0; rd < 2; rd++) {
        uint32_t oA[8], oB[8];
#pragma unroll
        for (int i = 0; i < 8; i++) {
          const uint2* k4 = &kk[rd][i];
          uint32_t a = badd2(badd2(badd2(bmul2(k4[0].x, wA[3]), bmul2(k4[1].x, wA[2])), bmul2(k4[2].x, wA[1])), bmul2(k4[3].x, wA[0]));
          uint32_t c = badd2(badd2(badd2(bmul2(k4[0].y, wB[3]), bmul2(k4[1].y, wB[2])), bmul2(k4[2].y, wB[1])), bmul2(k4[3].y, wB[0]));
          oA[i] = bmul2(a, vv[rd][i].x); oB[i] = bmul2(c, vv[rd][i].y);
        }
        if (rd == 0) mbar_wait(BAR(B_SP0DONE), 0);
        const int chunk = (4 * rd + w) ^ 1, rot = (lane >> 1) & 3;
#pragma unroll
        for (int q = 0; q < 4; q++) {
          const int cq = (q + rot) & 3, row = 4 * lane + cq;
          const uint32_t sel = (cq & 1) ? 0x7632 : 0x5410;
          const bool useB = cq & 2;
          sts128(sb + SM_CVA + CV_KVST + row * 128 + ((chunk ^ (row & 7)) * 16),
                 __byte_perm(useB ? oB[7] : oA[7], useB ? oB[6] : oA[6], sel), __byte_perm(useB ? oB[5] : oA[5], useB ? oB[4] : oA[4], sel),
                 __byte_perm(useB ? oB[3] : oA[3], useB ? oB[2] : oA[2], sel), __byte_perm(useB ? oB[1] : oA[1], useB ? oB[0] : oA[0], sel));
        }
      }
    }
    {
      const uint32_t cv = sb + SM_CVA;
      if (t128 < 48) sts128(cv + (t128 & 1) * KV_HALF + (t128 >> 1) * 16, 0, 0, 0, 0);
      if (t128 >= 64 && t128 < 68) sts128(cv + CV_H + (t128 & 1) * CV_HBUF + (t128 & 2) * 8, 0, 0, 0, 0);
      fence_async_smem();
      named_bar<2, 128>();
      if (t128 >= 64) asm volatile("prefetch.global.L2 [%0];" :: "l"(P.ssm_k + (size_t)(4 * b) * SEQ + t128 * 64));
      if (t128 == 96) {
        tma_store_2d(&maps.kv, 64 * (b >> 2), 128 * (b & 3), cv + CV_KVST);
        asm volatile("cp.async.bulk.commit_group;" ::: "memory");
        publish_bulk(&g_cnt[(C_KV + (b & 3)) * 32]);
      }
      if (t128 == 0) {
        mbar_expect_tx(BAR(B_HKA), 8192);
        bulk_load(cv + CV_H + 32, P.ssm_k + (size_t)(4 * b) * SEQ, 4096, BAR(B_HKA));
        bulk_load(cv + CV_H + CV_HBUF + 32, P.ssm_k + (size_t)(4 * b + 1) * SEQ, 4096, BAR(B_HKA));
      }
      mbar_wait(BAR(B_HKA), 0);
      named_bar<2, 128>();
    }
  } else {
    reg_inc<168>();
    const int tid = fresh_tid(), lane = tid & 31;
    const int wgi = wg - 1, w = warp & 3, g = lane >> 2, t = lane & 3;
    const uint32_t alo = desc_lo(sb + SM_X + wgi * 8192, 16);
    __nv_bfloat16* hblk = g_h + (size_t)r * 28 * 8192 + (8 * wgi + 2 * w) * 512 + t * 64 + g * 8;
#define HDST(ap) (hblk + ((ap) >> 1) * 8192 + ((ap) & 1) * 256)
    const uint32_t cs = sb + SM_CS + t * 16;
    float4 st4, cpre[2];
    uint32_t H[4];
    float acc0[64], accB[64];
    const uint32_t blo = desc_lo(sb + SM_RING, 8192);
#define G1_RELEASE(S) { if (lane == 0) { if ((S) < 4) mbar_arrive(BAR(B_WEMPTY + (S))); else if ((S) == 5) mbar_arrive(BAR(B_SP0DONE)); else if ((S) >= 6) mbar_arrive(BAR(B_WEMPTY + (((S) - 6) & 3))); } }
#define G1_WAIT(S) { if ((S) < 8) mbar_wait_nt(BAR(B_XFULL + (S)), 0); else mbar_wait_nt(BAR(B_WFULL + (((S) - 6) & 3)), (((S) - 8) >> 2) & 1); }
#define G1_STAGE(ACC, SP, i, ...) { \
      const int S = 8 * (SP) + (i); \
      const int slot = S < 6 ? S : (S - 6) & 3; \
      wgmma_fence(); \
      wgmma_n128_t01<HI_SW128, HI_SW128, 0, 0>(ACC, alo + (i) * 1024, blo + slot * 1024, (i) > 0); \
      wgmma_n128_t01<HI_SW128, HI_SW128, 2, 128>(ACC, alo + (i) * 1024, blo + slot * 1024, 1); \
      wgmma_n128_t01<HI_SW128, HI_SW128, 4, 256>(ACC, alo + (i) * 1024, blo + slot * 1024, 1); \
      wgmma_n128_t01<HI_SW128, HI_SW128, 6, 384>(ACC, alo + (i) * 1024, blo + slot * 1024, 1); \
      wgmma_commit(); \
      if (S > 0) { wgmma_wait<1>(); G1_RELEASE(S - 1) } \
      G1_WAIT(S + 1) \
      __VA_ARGS__ }
#define EPI(TI, Q, GP, UP, AP, NEXT) { h_epilogue<Q>(GP, UP, cpre, st4, HDST(AP), H, (NEXT) > 0 ? cs + (NEXT) : 0u); }
#define CPRE(OFF) { cpre[0] = lds128f(cs + (OFF)); cpre[1] = lds128f(cs + (OFF) + 64); }
#define HDONE(q) { __syncwarp(); if (lane == 0) mbar_arrive(BAR(B_HDONE + q)); }
    G1_WAIT(0)
#pragma unroll 1
    for (int i = 0; i < 8; i++) {
      G1_STAGE(acc0, 0, i)
      if (i == KV_GATE && tid == 128) mbar_arrive(BAR(B_KVGATE));
    }
    G1_STAGE(accB, 1, 0)
#pragma unroll 1
    for (int i = 1; i < 3; i++) G1_STAGE(accB, 1, i)
    G1_STAGE(accB, 1, 3)
    mbar_wait_nt(BAR(B_PREP), 0);
    {
      const float2 sv = lds64f(sb + SM_ST + (16 * g + 8 * wgi + 2 * w) * 4);
      const uint32_t s1 = __float_as_uint(sv.x), s2 = __float_as_uint(sv.y);
      const float r1 = 1.f / bf_hi(s1), r2_ = 1.f / bf_hi(s2);
      st4 = make_float4(bf_lo(s1), r1 * r1, bf_lo(s2), r2_ * r2_);
    }
    CPRE(0)
    G1_STAGE(accB, 1, 4, EPI(0, 0, acc0, acc0 + 32, 2 * atom1, 128))
    G1_STAGE(accB, 1, 5, EPI(1, 1, acc0, acc0 + 32, 2 * atom1, 256))
    G1_STAGE(accB, 1, 6, EPI(2, 0, acc0 + 16, acc0 + 48, 2 * atom1 + 1, 384))
    G1_STAGE(accB, 1, 7, EPI(3, 1, acc0 + 16, acc0 + 48, 2 * atom1 + 1, 0) HDONE(0))
    float* const accA = acc0;
    G1_STAGE(accA, 2, 0)
#pragma unroll 1
    for (int i = 1; i < 3; i++) G1_STAGE(accA, 2, i)
    G1_STAGE(accA, 2, 3)
    mbar_wait_nt(BAR(B_PREP1), 0);
    CPRE(512)
    G1_STAGE(accA, 2, 4, EPI(4, 0, accB, accB + 32, 2 * atom1 + 2, 640))
    G1_STAGE(accA, 2, 5, EPI(5, 1, accB, accB + 32, 2 * atom1 + 2, 768))
    G1_STAGE(accA, 2, 6, EPI(6, 0, accB + 16, accB + 48, 2 * atom1 + 3, 896))
    G1_STAGE(accA, 2, 7, EPI(7, 1, accB + 16, accB + 48, 2 * atom1 + 3, 0) HDONE(1))
    mbar_wait_nt(BAR(B_PREP2), 0);
    CPRE(1024)
    float accH[32];
    {
      const uint32_t hlo = desc_lo(sb + SM_RING, 4096);
#define G1H_MMA(i, BO) \
      wgmma_n64_t01<HI_SW128, HI_SW64, (i) * 1024, BO>(accH, alo, hlo, (i) > 0); \
      wgmma_n64_t01<HI_SW128, HI_SW64, (i) * 1024 + 2, BO + 64>(accH, alo, hlo, 1); \
      wgmma_n64_t01<HI_SW128, HI_SW64, (i) * 1024 + 4, BO + 128>(accH, alo, hlo, 1); \
      wgmma_n64_t01<HI_SW128, HI_SW64, (i) * 1024 + 6, BO + 192>(accH, alo, hlo, 1);
#define G1H_PAIR(i, ...) { \
      constexpr int slot = (2 + (i) / 2) & 3; \
      wgmma_fence(); \
      G1H_MMA(i, slot * 1024) G1H_MMA((i) + 1, slot * 1024 + 512) \
      wgmma_commit(); \
      wgmma_wait<1>(); \
      if (lane == 0) mbar_arrive(BAR((i) == 0 ? B_WEMPTY + 1 : B_XFREE + (i) - 1)); \
      if ((i) < 6) G1_WAIT(25 + (i) / 2) \
      __VA_ARGS__ }
      G1H_PAIR(0, EPI(8, 0, accA, accA + 32, 2 * atomS, 1152))
      G1H_PAIR(2, EPI(9, 1, accA, accA + 32, 2 * atomS, 1280))
      G1H_PAIR(4, EPI(10, 0, accA + 16, accA + 48, 2 * atomS + 1, 1408))
      G1H_PAIR(6, EPI(11, 1, accA + 16, accA + 48, 2 * atomS + 1, 1536))
      wgmma_wait<0>();
      if (lane == 0) mbar_arrive(BAR(B_XFREE + 7));
    }
    const int t128 = tid & 127;
    EPI(12, 0, accH, accH + 16, grpH, 1664) EPI(13, 1, accH, accH + 16, grpH, 0) HDONE(2)
    if (wgi == 0) {
      reg_inc<208>();
      float acc[64];
      const uint32_t a2 = desc_lo(sb + 16384, 8192), b2 = desc_lo(sb, 128);
      int buf = 0, ph = 0, prev = 0;
#define G2_STEP(i) { \
        mbar_wait_nt(BAR(B_G2FULL + buf), ph); \
        const uint32_t da = a2 + (g2_off(buf) >> 4), db = b2 + (g2_off(buf) >> 4); \
        const bool rel = (i) > 0 && (i) != G2_HOLD1 && (i) != G2_HOLD2; \
        wgmma_fence(); \
        wgmma_n128_t10<HI_SW128, HI_BLK, 0, 0>(acc, da, db, (i) > 0); \
        wgmma_n128_t10<HI_SW128, HI_BLK, 128, 16>(acc, da, db, 1); \
        wgmma_n128_t10<HI_SW128, HI_BLK, 256, 32>(acc, da, db, 1); \
        wgmma_n128_t10<HI_SW128, HI_BLK, 384, 48>(acc, da, db, 1); \
        wgmma_commit(); \
        { wgmma_wait<1>(); if (rel && lane == 0) mbar_arrive(BAR(B_G2EMPTY + prev)); } \
        prev = buf; if (++buf == G2_NB) { buf = 0; ph ^= 1; } }
#pragma unroll 1
      for (int i = 0; i < 28; i++) {
        if (i == G2_HOLD1 || i == G2_HOLD2) {
          wgmma_wait<0>(); if (lane == 0) mbar_arrive(BAR(B_G2EMPTY + prev));
          mbar_wait_nt(BAR(B_CVP + (i == G2_HOLD2)), 0);
        }
        G2_STEP(i)
      }
      const int mi = lane >> 3, rr = lane & 7;
      uint32_t X[32], XN[32];
      const uint32_t ta = sb + SM_FX + (8 * (mi >> 1) + rr) * 128 + (((2 * w + (mi & 1)) ^ rr) * 16);
      mbar_wait_nt(BAR(B_FIN), 0);
      mbar_wait_nt(BAR(B_ST2), 0);
#pragma unroll
      for (int q = 0; q < 8; q++) {
        ldmatrix_x4_t(ta + q * 2048, X[4 * q], X[4 * q + 1], X[4 * q + 2], X[4 * q + 3]);
#pragma unroll
        for (int jj = 0; jj < 2; jj++) {
          const float4 sf = lds128f(sb + SM_CS + (16 * q + 8 * jj + 2 * t) * 8);
          const uint32_t mm = pack_bf16(sf.x, sf.z);
#pragma unroll
          for (int hi = 0; hi < 2; hi++) {
            const uint32_t dd = bsub2(X[4 * q + 2 * jj + hi], mm);
            XN[4 * q + 2 * jj + hi] = pack_bf16(bf_lo(dd) * sf.y, bf_hi(dd) * sf.w);
          }
        }
      }
      wgmma_wait<0>();
      const uint32_t za = sb + SM_FZ + (16 * w + 8 * (mi & 1) + rr) * 128;
#pragma unroll 1
      for (int pass = __all_sync(0xffffffffu, mbar_test(BAR(B_FINZ), 0)) ? 1 : 0; pass < 2; pass++) {
        if (pass) mbar_wait_nt(BAR(B_FINZ), 0);
#pragma unroll
        for (int q = 0; q < 8; q++) {
          uint32_t z[4];
          ldmatrix_x4(za + (q >> 2) * 8192 + ((((2 * q + (mi >> 1)) & 7) ^ rr) * 16), z[0], z[1], z[2], z[3]);
#pragma unroll
          for (int e = 0; e < 4; e++) z[e] = badd2(badd2(X[4 * q + e], bmul2(XN[4 * q + e], z[e])), pack_bf16(acc[8 * q + 2 * e], acc[8 * q + 2 * e + 1]));
          stmatrix_x4_t(ta + q * 2048, z[0], z[1], z[2], z[3]);
        }
      }
      fence_async_smem();
      named_bar<5, 128>();
      if (t128 == 0) {
        tma_store_3d(&maps.out, nb * 64, 8 * r2, 0, sb + SM_FX);
        asm volatile("cp.async.bulk.commit_group;\ncp.async.bulk.wait_group.read 0;" ::: "memory");
        atomicAdd(&g_cnt[C_DONE * 32], 1u);
      }
      return;
    }
    reg_dec<128>();
    mbar_wait_nt(BAR(B_HKB), 0);
  }
  {
    const int t128 = fresh_tid() & 127, lane = t128 & 31, sB = wg == 2;
    const uint32_t cv = sb + (sB ? SM_CVB : SM_CVA);
    const uint32_t Dw = ldg32(P.ssm_D + 4 * b + 2 * sB);
    const int kc = (t128 & 96) + 2 * (lane & 15) + (lane >> 4);
    const uint4* kvsrc = g_kvT + (size_t)(4 * b + 2 * sB) * 256 + kc;
    conv_pre(cv, cv + CV_H);
    uint4 kp0, kp1;
    if (!sB) { mbar_wait_nt(BAR(B_KVRDY), 0); kp0 = ld_relaxed128(kvsrc); kp1 = ld_relaxed128(kvsrc + 128); }
#pragma unroll 1
    for (int ci = 0; ci < 2; ci++) {
      if (ci || !sB) {
        const uint32_t kd0 = cv + (kc & 1) * KV_HALF + KV_PAD + (kc >> 1) * 16;
        sts128(kd0, kp0.x, kp0.y, kp0.z, kp0.w);
        sts128(kd0 + 1024, kp1.x, kp1.y, kp1.z, kp1.w);
      }
      conv_one(4 * b + 2 * sB + ci, cv, cv + CV_H + ci * CV_HBUF, sB ? 7 : 2, __byte_perm(Dw, Dw, ci ? 0x3232 : 0x1010), ci == 0, BAR(B_CVP + ci), [&](auto K) {
        if (K.value == 3 && ci == 0) { kp0 = ld_relaxed128(kvsrc + 256); kp1 = ld_relaxed128(kvsrc + 384); }
      });
    }
    if (t128 == 96) { publish_bulk(&g_cnt[(C_Z + (b >> 4)) * 32]); if (!sB) mbar_arrive(BAR(B_AFREE)); }
  }
}

typedef CUresult (*PFN_encodeTiled)(CUtensorMap*, CUtensorMapDataType, cuuint32_t, void*, const cuuint64_t*, const cuuint64_t*,
                                    const cuuint32_t*, const cuuint32_t*, CUtensorMapInterleave, CUtensorMapSwizzle,
                                    CUtensorMapL2promotion, CUtensorMapFloatOOBfill);

bool encode(PFN_encodeTiled fn, CUtensorMap* m, const void* base, int rank, const cuuint64_t* dims, const cuuint64_t* strides, const cuuint32_t* box,
            CUtensorMapSwizzle sw = CU_TENSOR_MAP_SWIZZLE_128B) {
  cuuint32_t es[5] = {1, 1, 1, 1, 1};
  return fn(m, CU_TENSOR_MAP_DATA_TYPE_BFLOAT16, rank, const_cast<void*>(base), dims, strides, box, es, CU_TENSOR_MAP_INTERLEAVE_NONE,
            sw, CU_TENSOR_MAP_L2_PROMOTION_L2_256B, CU_TENSOR_MAP_FLOAT_OOB_FILL_NONE) == CUDA_SUCCESS;
}

}

extern "C" void kernel_launch(void* const* d_in, const int* in_sizes, int n_in, void* d_out, int out_size) {
  static Maps maps;
  static Ptrs P;
  static const void* key[11] = {nullptr};
  bool same = (key[10] == d_out);
  for (int i = 0; i < 10; i++) same = same && (key[i] == d_in[i]);
  if (!same) {
    void* fnp = nullptr;
    cudaDriverEntryPointQueryResult q;
    cudaGetDriverEntryPoint("cuTensorMapEncodeTiled", &fnp, cudaEnableDefault, &q);
    PFN_encodeTiled fn = (PFN_encodeTiled)fnp;
    const __nv_bfloat16* wg = (const __nv_bfloat16*)d_in[7];
    const __nv_bfloat16* wu = (const __nv_bfloat16*)d_in[8];
    P.x = (const __nv_bfloat16*)d_in[0]; P.k = (const __nv_bfloat16*)d_in[1]; P.v = (const __nv_bfloat16*)d_in[2];
    P.shift_k = (const __nv_bfloat16*)d_in[3]; P.ssm_k = (const __nv_bfloat16*)d_in[4]; P.ssm_D = (const __nv_bfloat16*)d_in[5];
    P.w0 = wg < wu ? wg : wu; P.w1 = wg < wu ? wu : wg;
    P.wd = (const __nv_bfloat16*)d_in[9];
    const cuuint64_t gu = (cuuint64_t)((const char*)P.w1 - (const char*)P.w0);
    bool ok = true;
    void *pz, *pkv;
    cudaGetSymbolAddress(&pkv, g_kvT);
    { cuuint64_t d[2] = {2048, 512}, s[1] = {4096}; cuuint32_t bx[2] = {64, 128}; ok &= encode(fn, &maps.kv, pkv, 2, d, s, bx); }
    cudaGetSymbolAddress(&pz, g_zT);
    { cuuint64_t d[2] = {2048, 512}, s[1] = {4096}; cuuint32_t bx[2] = {64, 64}; ok &= encode(fn, &maps.z, pz, 2, d, s, bx); }
    { cuuint64_t d[3] = {512, 128, 16}, s[2] = {16384, 1024}; cuuint32_t bx[3] = {64, 8, 16}; ok &= encode(fn, &maps.x, P.x, 3, d, s, bx); }
    { cuuint64_t d[3] = {512, 128, 16}, s[2] = {16384, 1024}; cuuint32_t bx[3] = {64, 8, 16}; ok &= encode(fn, &maps.out, d_out, 3, d, s, bx); }
    { cuuint64_t d[3] = {1792, 512, 2}, s[2] = {3584, gu}; cuuint32_t bx[3] = {64, 64, 2}; ok &= encode(fn, &maps.w, P.w0, 3, d, s, bx); }
    { cuuint64_t d[3] = {1792, 512, 2}, s[2] = {3584, gu}; cuuint32_t bx[3] = {32, 64, 2}; ok &= encode(fn, &maps.wh, P.w0, 3, d, s, bx, CU_TENSOR_MAP_SWIZZLE_64B); }
    { cuuint64_t d[5] = {512, 2, 4, 4, 56}, s[4] = {1024, 8192, 2048, 32768}; cuuint32_t bx[5] = {64, 2, 4, 4, 2}; ok &= encode(fn, &maps.wd, P.wd, 5, d, s, bx); }
    (void)ok;
    cudaFuncSetAttribute(fused_kernel, cudaFuncAttributeMaxDynamicSharedMemorySize, SMEM_TOTAL);
    for (int i = 0; i < 10; i++) key[i] = d_in[i];
    key[10] = d_out;
  }
  cudaLaunchConfig_t cfg = {};
  cfg.gridDim = dim3(NCTA + 4); cfg.blockDim = dim3(512); cfg.dynamicSmemBytes = SMEM_TOTAL; cfg.stream = cudaStreamPerThread;
  cudaLaunchAttribute at[1];
  at[0].id = cudaLaunchAttributeClusterDimension; at[0].val.clusterDim.x = 2; at[0].val.clusterDim.y = 1; at[0].val.clusterDim.z = 1;
  cfg.attrs = at; cfg.numAttrs = 1;
  cudaLaunchKernelEx(&cfg, fused_kernel, maps, P);
}
```
